```python
import torch

def _softmax(x, axis=-1):
    return torch.softmax(x, dim=axis)
def _gelu(x):
    return torch.nn.functional.gelu(x, approximate="tanh")
def _silu(x):
    return torch.nn.functional.silu(x)
def _sigmoid(x):
    return torch.sigmoid(x)
def _layernorm(x, axis=-1, eps=1e-5):
    m = x.mean(dim=axis, keepdim=True)
    v = x.var(dim=axis, keepdim=True, unbiased=False)
    return (x - m) / torch.sqrt(v + eps)
def _scatter_add(tgt, idx, src, axis=0):
    return tgt.clone().index_add_(axis, idx, src)
def _segment_sum(src, seg, n):
    out = torch.zeros((n,) + src.shape[1:], dtype=src.dtype)
    return out.index_add_(0, seg, src)
def _pad(x, pw):
    flat = tuple(v for pair in reversed(pw) for v in pair)
    return torch.nn.functional.pad(x, flat)

kernel_name = 'recurrent_scan__sliding_block_cached__glu_gated_swiglu__prompt'

def setup_inputs():

    _w = (lambda a: (lambda t: t.to(torch.bfloat16) if t.is_floating_point() else t)(torch.as_tensor(a)))
    def _A_setup():
        B, Sq, D = 1, 2048, 640
        Hq, Hkv, Sk, Dh = 32, 32, 2048, 128
        assert Hq % Hkv == 0, (Hq, Hkv)
        return {
            "x": _w((lambda *s: torch.randn(*s, dtype=torch.bfloat16) * 0.05)(B, Sq, D)),
            "k_cache": _w((lambda *s: torch.randn(*s, dtype=torch.bfloat16) * 1.6)(B, Hkv, Sk, Dh)),
            "v_cache": _w((lambda *s: torch.randn(*s, dtype=torch.bfloat16) * 1.6)(B, Hkv, Sk, Dh)),
            "wq": _w((lambda *s: torch.randn(*s, dtype=torch.bfloat16) * 1.6)(D, Hq * Dh) * (D ** -0.5)),
            "wo": _w((lambda *s: torch.randn(*s, dtype=torch.bfloat16) * 1.6)(Hq * Dh, D) * ((Hq * Dh) ** -0.5)),
        }
    _A_in = _A_setup()

    def _B_setup():
        B, S, D, F = 1, 2048, 640, 1728
        return {
            "x": _w((lambda *s: torch.randn(*s, dtype=torch.bfloat16) * 0.05)(B, S, D)),
            "w1": _w((lambda *s: torch.randn(*s, dtype=torch.bfloat16) * 0.2)(D, F) * (2.0 / D) ** 0.5),
            "w3": _w((lambda *s: torch.randn(*s, dtype=torch.bfloat16) * 0.2)(D, F) * (2.0 / D) ** 0.5),
            "w2": _w((lambda *s: torch.randn(*s, dtype=torch.bfloat16) * 0.2)(F, D) * (2.0 / F) ** 0.5),
        }
    _B_in = _B_setup()

    return {
        "A_x": _A_in["x"],
        "A_k_cache": _A_in["k_cache"],
        "A_v_cache": _A_in["v_cache"],
        "A_wq": _A_in["wq"],
        "A_wo": _A_in["wo"],
        "B_x": _B_in["x"],
        "B_w1": _B_in["w1"],
        "B_w3": _B_in["w3"],
        "B_w2": _B_in["w2"],
    }

def reference(A_x, A_k_cache, A_v_cache, A_wq, A_wo, B_x, B_w1, B_w3, B_w2):
    def _A_ref(x, k_cache, v_cache, wq, wo):
        B, Sq, D = x.shape
        Hq, Dh = 32, 128
        Hkv, Sk = k_cache.shape[1], k_cache.shape[2]
        W = min(4096, max(256, Sk // 4))
        rep = Hq // Hkv
        q = (lambda x, *d: x.permute(*d))((x @ wq).reshape(B, Sq, Hq, Dh), 0, 2, 1, 3)
        k = (lambda x, n, axis: torch.repeat_interleave(x, n, dim=axis))(k_cache[:, :, Sk - W:, :], rep, axis=1)
        v = (lambda x, n, axis: torch.repeat_interleave(x, n, dim=axis))(v_cache[:, :, Sk - W:, :], rep, axis=1)
        scores = torch.einsum("bhqd,bhkd->bhqk", q, k) * (Dh ** -0.5)
        p = _softmax(scores, axis=-1)
        o = torch.einsum("bhqk,bhkd->bhqd", p, v)
        return (lambda x, *d: x.permute(*d))(o, 0, 2, 1, 3).reshape(B, Sq, Hq * Dh) @ wo

    def _B_ref(x, w1, w3, w2):
        gate = torch.einsum("bsd,df->bsf", x, w1)
        up = torch.einsum("bsd,df->bsf", x, w3)
        h = _silu(gate) * up
        out = torch.einsum("bsf,fd->bsd", h, w2)
        return out

    x = A_x
    xn = _layernorm(x, axis=-1)
    s = _A_ref(xn, A_k_cache, A_v_cache, A_wq, A_wo)
    g = _silu(_B_ref(xn, B_w1, B_w3, B_w2))
    return x + s * g
```

```cpp
#include <cuda_runtime.h>
#include <cuda_bf16.h>
#include <cuda.h>
#include <stdint.h>

namespace fk {

constexpr int D_MODEL = 640, NHEAD = 32, DH = 128, F_FF = 1728, SK = 2048, WIN = 512;
constexpr int MT = 16;
constexpr int KB_D = 10;
constexpr int NCHUNK = 27;
constexpr int MAX_PAIRS = 66;
constexpr int MAX_SEG = 4;
constexpr int MAX_T4 = 4;

constexpr float SM_SCALE = 0.08838834764831845f * 1.4426950408889634f;
constexpr float SM_LAZY = 16.0f;

constexpr uint32_t SLOT = 16384;
constexpr uint32_t XN_OFF = 65536;
constexpr uint32_t XN_WG = 81920;
constexpr uint32_t STASH_OFF = 32768;
constexpr uint32_t T4_STAGE = 36864;
constexpr int T4_STAGES = 6;
constexpr uint32_t BAR_OFF = 229376;
constexpr uint32_t SMEM_BYTES = BAR_OFF + 512;
constexpr int B_FULL = 0, B_EMPTY = 8, B_XFULL = 16, B_XDEAD = 26, B_ADONE = 27, B_FULL4 = 28, B_EMPTY4 = 34, B_SIG = 40, B_SFREE = 42, B_COUNT = 43;

struct Seg { uint8_t p, c0, nc, head0; };
struct T4Task { uint8_t type, p, j, pad; };
struct PairSched { uint8_t nseg, nt4, pad0, pad1; Seg seg[MAX_SEG]; T4Task t4[MAX_T4]; };
struct Params {
  const __nv_bfloat16* x;
  uint8_t* xn; unsigned int *cnt_xn, *done;
  uint8_t *h, *o, *g; unsigned int *cnt_h, *cnt_o, *cnt_g;
  __nv_bfloat16* out;
  uint8_t head_order[NHEAD];
  PairSched sched[MAX_PAIRS];
};

__device__ __align__(1024) uint8_t g_xn[MT * 2 * KB_D * 8192];
__device__ __align__(1024) uint8_t g_h[MT * NCHUNK * 16384];
__device__ __align__(1024) uint8_t g_o[MT * 64 * 16384];
__device__ __align__(1024) uint8_t g_g[MT * 4 * 40960];
__device__ unsigned int g_cnt_xn[MT * 32];
__device__ unsigned int g_cnt_h[MT * 32];
__device__ unsigned int g_cnt_o[MT * NHEAD];
__device__ unsigned int g_cnt_g[MT * 4];
__device__ unsigned int g_done;

__device__ __forceinline__ uint32_t smem_u32(const void* p) { return (uint32_t)__cvta_generic_to_shared(p); }
__device__ __forceinline__ void mbar_init(uint32_t bar, uint32_t cnt) { asm volatile("mbarrier.init.shared::cta.b64 [%0], %1;" :: "r"(bar), "r"(cnt) : "memory"); }
__device__ __forceinline__ void mbar_expect_tx(uint32_t bar, uint32_t bytes) { asm volatile("mbarrier.arrive.expect_tx.shared::cta.b64 _, [%0], %1;" :: "r"(bar), "r"(bytes) : "memory"); }
__device__ __forceinline__ void mbar_arrive(uint32_t bar) { asm volatile("mbarrier.arrive.shared::cta.b64 _, [%0];" :: "r"(bar) : "memory"); }
__device__ __forceinline__ void mbar_arrive_both(uint32_t bar) {
  asm volatile("{\n.reg .b32 r0, r1;\n"
               "mapa.shared::cluster.u32 r0, %0, 0;\n"
               "mapa.shared::cluster.u32 r1, %0, 1;\n"
               "mbarrier.arrive.shared::cluster.b64 _, [r0];\n"
               "mbarrier.arrive.shared::cluster.b64 _, [r1];\n}" :: "r"(bar) : "memory");
}
__device__ __forceinline__ void mbar_wait(uint32_t bar, uint32_t parity) {
  asm volatile("{\n.reg .pred p;\n.reg .u32 n;\nmov.u32 n, 0;\n"
               "W_LOOP:\n"
               "mbarrier.try_wait.parity.shared::cta.b64 p, [%0], %1;\n"
               "@p bra W_DONE;\n"
               "add.u32 n, n, 1;\n"
               "setp.gt.u32 p, n, 4194304;\n"
               "@p trap;\n"
               "bra W_LOOP;\n"
               "W_DONE:\n}" :: "r"(bar), "r"(parity)
               : "memory");
}
__device__ __forceinline__ uint32_t mbar_test(uint32_t bar, uint32_t parity) {
  uint32_t ok;
  asm volatile("{\n.reg .pred p;\nmbarrier.test_wait.parity.shared::cta.b64 p, [%1], %2;\nselp.u32 %0, 1, 0, p;\n}" : "=r"(ok) : "r"(bar), "r"(parity) : "memory");
  return ok;
}
__device__ __forceinline__ void mbar_wait_tok(uint32_t bar, uint32_t parity, uint32_t tok) { if (!tok) mbar_wait(bar, parity); }
__device__ __forceinline__ void bulk_store(void* dst, uint32_t src, uint32_t bytes) {
  asm volatile("cp.async.bulk.global.shared::cta.bulk_group [%0], [%1], %2;" :: "l"(dst), "r"(src), "r"(bytes) : "memory");
}
__device__ __forceinline__ void flag_wait(const unsigned int* ptr, unsigned int target) {
  asm volatile("{\n.reg .pred p;\n.reg .u32 n, v;\n.reg .s32 d;\nmov.u32 n, 0;\n"
               "F_LOOP:\n"
               "ld.acquire.gpu.global.u32 v, [%0];\n"
               "sub.s32 d, v, %1;\n"
               "setp.ge.s32 p, d, 0;\n"
               "@p bra F_DONE;\n"
               "add.u32 n, n, 1;\n"
               "setp.gt.u32 p, n, 16777216;\n"
               "@p trap;\n"
               "bra F_LOOP;\n"
               "F_DONE:\n}" :: "l"(ptr), "r"(target)
               : "memory");
}
__device__ __forceinline__ void flag_wait_spin(const unsigned int* ptr, unsigned int target) {
  asm volatile("{\n.reg .pred p;\n.reg .u32 n, v;\n.reg .s32 d;\nmov.u32 n, 0;\n"
               "G_LOOP:\n"
               "ld.relaxed.gpu.global.u32 v, [%0];\n"
               "sub.s32 d, v, %1;\n"
               "setp.ge.s32 p, d, 0;\n"
               "@p bra G_DONE;\n"
               "add.u32 n, n, 1;\n"
               "setp.gt.u32 p, n, 16777216;\n"
               "@p trap;\n"
               "bra G_LOOP;\n"
               "G_DONE:\n}" :: "l"(ptr), "r"(target)
               : "memory");
}
__device__ __forceinline__ bool elect_one() {
  uint32_t p;
  asm volatile("{\n.reg .pred P;\nelect.sync _|P, 0xffffffff;\nselp.u32 %0, 1, 0, P;\n}" : "=r"(p));
  return p != 0;
}
__device__ __forceinline__ uint32_t poll_flags(const unsigned int* p, unsigned int target) {
  unsigned int v;
  asm volatile("ld.acquire.gpu.global.u32 %0, [%1];" : "=r"(v) : "l"(p) : "memory");
  const uint32_t m = __ballot_sync(0xffffffffu, (int)(v - target) >= 0);
  asm volatile("fence.proxy.async.global;" ::: "memory");
  return m;
}
__device__ __forceinline__ void flag_signal(unsigned int* p) {
  asm volatile("red.release.gpu.global.add.u32 [%0], 1;" :: "l"(p) : "memory");
}
__device__ __forceinline__ void tma_2d_mc(uint32_t dst, const CUtensorMap* map, uint32_t bar, int c0, int c1) {
  asm volatile("cp.async.bulk.tensor.2d.shared::cluster.global.mbarrier::complete_tx::bytes.multicast::cluster [%0], [%1, {%3, %4}], [%2], %5;"
               :: "r"(dst), "l"(map), "r"(bar), "r"(c0), "r"(c1), "h"((uint16_t)3) : "memory");
}
__device__ __forceinline__ void bulk_load(uint32_t dst, const void* src, uint32_t bytes, uint32_t bar) {
  asm volatile("cp.async.bulk.shared::cluster.global.mbarrier::complete_tx::bytes [%0], [%1], %2, [%3];"
               :: "r"(dst), "l"(src), "r"(bytes), "r"(bar) : "memory");
}
__device__ __forceinline__ void wg_fence() { asm volatile("wgmma.fence.sync.aligned;" ::: "memory"); }
__device__ __forceinline__ void wg_commit() { asm volatile("wgmma.commit_group.sync.aligned;" ::: "memory"); }
template <int N> __device__ __forceinline__ void wg_wait() { asm volatile("wgmma.wait_group.sync.aligned %0;" :: "n"(N) : "memory"); }
template <int N> __device__ __forceinline__ void reg_fence(float (&a)[N]) {
#pragma unroll
  for (int i = 0; i < N; i++) asm volatile("" : "+f"(a[i]) :: "memory");
}
template <int N> __device__ __forceinline__ void reg_fence_u(uint32_t (&a)[N][4]) {
#pragma unroll
  for (int i = 0; i < N; i++) asm volatile("" : "+r"(a[i][0]), "+r"(a[i][1]), "+r"(a[i][2]), "+r"(a[i][3]) :: "memory");
}
__device__ __forceinline__ void bar_sync(int id, int n) { asm volatile("bar.sync %0, %1;" :: "r"(id), "r"(n) : "memory"); }
__device__ __forceinline__ void bar_arrive(int id, int n) { asm volatile("bar.arrive %0, %1;" :: "r"(id), "r"(n) : "memory"); }
__device__ __forceinline__ uint32_t pack_bf16(float lo, float hi) {
  uint32_t r; asm("cvt.rn.bf16x2.f32 %0, %1, %2;" : "=r"(r) : "f"(hi), "f"(lo)); return r;
}
__device__ __forceinline__ uint32_t mul_bf16x2(uint32_t a, uint32_t b) { uint32_t r; asm("mul.rn.bf16x2 %0, %1, %2;" : "=r"(r) : "r"(a), "r"(b)); return r; }
__device__ __forceinline__ uint32_t add_bf16x2(uint32_t a, uint32_t b) { uint32_t r; asm("add.rn.bf16x2 %0, %1, %2;" : "=r"(r) : "r"(a), "r"(b)); return r; }
__device__ __forceinline__ float bf_lo(uint32_t u) { return __uint_as_float(u << 16); }
__device__ __forceinline__ float bf_hi(uint32_t u) { return __uint_as_float(u & 0xFFFF0000u); }
__device__ __forceinline__ float ex2(float x) { float y; asm("ex2.approx.ftz.f32 %0, %1;" : "=f"(y) : "f"(x)); return y; }
__device__ __forceinline__ uint32_t silu_pair(uint32_t v) {
  float a, b;
  asm("max.NaN.f32 %0, %1, 0fC22EA3D7;" : "=f"(a) : "f"(bf_lo(v)));
  asm("max.NaN.f32 %0, %1, 0fC22EA3D7;" : "=f"(b) : "f"(bf_hi(v)));
  const float da = 1.0f + ex2(a * -1.4426950408889634f), db = 1.0f + ex2(b * -1.4426950408889634f);
  float r; asm("rcp.approx.ftz.f32 %0, %1;" : "=f"(r) : "f"(da * db));
  return pack_bf16(a * (db * r), b * (da * r));
}
__device__ __forceinline__ void st_global_u32(void* p, uint32_t v) { asm volatile("st.global.u32 [%0], %1;" :: "l"(p), "r"(v) : "memory"); }
__device__ __forceinline__ float round_bf16(float x) { return __bfloat162float(__float2bfloat16_rn(x)); }

__host__ __device__ constexpr uint32_t desc_lo_lbo(uint32_t lbo) { return (lbo >> 4) << 16; }
constexpr uint32_t desc_hi(uint32_t sbo, uint32_t swz) { return (sbo >> 4) | (swz << 30); }
constexpr uint32_t HI_SW128 = desc_hi(1024, 1);
constexpr uint32_t HI_NOSWZ = desc_hi(1024, 0);
constexpr uint32_t HI_SW64 = desc_hi(512, 2);

__device__ __forceinline__ void wgmma_ss_n128_bt(float (&d)[64], uint32_t da_lo, uint32_t da_hi, uint32_t db_lo, uint32_t db_hi, int scale_d) {
  asm volatile("{\n.reg .pred p;\n.reg .b64 da, db;\nsetp.ne.b32 p, %68, 0;\nmov.b64 da, {%64, %65};\nmov.b64 db, {%66, %67};\n"
    "wgmma.mma_async.sync.aligned.m64n128k16.f32.bf16.bf16 "
    "{%0, %1, %2, %3, %4, %5, %6, %7, %8, %9, %10, %11, %12, %13, %14, %15, %16, %17, %18, %19, %20, %21, %22, %23, %24, %25, %26, %27, %28, %29, %30, %31, %32, %33, %34, %35, %36, %37, %38, %39, %40, %41, %42, %43, %44, %45, %46, %47, %48, %49, %50, %51, %52, %53, %54, %55, %56, %57, %58, %59, %60, %61, %62, %63}, "
    "da, db, p, 1, 1, 0, 1;\n}\n"
    : "+f"(d[0]), "+f"(d[1]), "+f"(d[2]), "+f"(d[3]), "+f"(d[4]), "+f"(d[5]), "+f"(d[6]), "+f"(d[7]), "+f"(d[8]), "+f"(d[9]), "+f"(d[10]), "+f"(d[11]), "+f"(d[12]), "+f"(d[13]), "+f"(d[14]), "+f"(d[15]), "+f"(d[16]), "+f"(d[17]), "+f"(d[18]), "+f"(d[19]), "+f"(d[20]), "+f"(d[21]), "+f"(d[22]), "+f"(d[23]), "+f"(d[24]), "+f"(d[25]), "+f"(d[26]), "+f"(d[27]), "+f"(d[28]), "+f"(d[29]), "+f"(d[30]), "+f"(d[31]), "+f"(d[32]), "+f"(d[33]), "+f"(d[34]), "+f"(d[35]), "+f"(d[36]), "+f"(d[37]), "+f"(d[38]), "+f"(d[39]), "+f"(d[40]), "+f"(d[41]), "+f"(d[42]), "+f"(d[43]), "+f"(d[44]), "+f"(d[45]), "+f"(d[46]), "+f"(d[47]), "+f"(d[48]), "+f"(d[49]), "+f"(d[50]), "+f"(d[51]), "+f"(d[52]), "+f"(d[53]), "+f"(d[54]), "+f"(d[55]), "+f"(d[56]), "+f"(d[57]), "+f"(d[58]), "+f"(d[59]), "+f"(d[60]), "+f"(d[61]), "+f"(d[62]), "+f"(d[63])
    : "r"(da_lo), "r"(da_hi), "r"(db_lo), "r"(db_hi), "r"(scale_d));
}
__device__ __forceinline__ void wgmma_rs_n128_bn(float (&d)[64], const uint32_t (&a)[4], uint32_t db_lo, uint32_t db_hi, int scale_d) {
  asm volatile("{\n.reg .pred p;\n.reg .b64 db;\nsetp.ne.b32 p, %70, 0;\nmov.b64 db, {%68, %69};\n"
    "wgmma.mma_async.sync.aligned.m64n128k16.f32.bf16.bf16 "
    "{%0, %1, %2, %3, %4, %5, %6, %7, %8, %9, %10, %11, %12, %13, %14, %15, %16, %17, %18, %19, %20, %21, %22, %23, %24, %25, %26, %27, %28, %29, %30, %31, %32, %33, %34, %35, %36, %37, %38, %39, %40, %41, %42, %43, %44, %45, %46, %47, %48, %49, %50, %51, %52, %53, %54, %55, %56, %57, %58, %59, %60, %61, %62, %63}, "
    "{%64, %65, %66, %67}, db, p, 1, 1, 0;\n}\n"
    : "+f"(d[0]), "+f"(d[1]), "+f"(d[2]), "+f"(d[3]), "+f"(d[4]), "+f"(d[5]), "+f"(d[6]), "+f"(d[7]), "+f"(d[8]), "+f"(d[9]), "+f"(d[10]), "+f"(d[11]), "+f"(d[12]), "+f"(d[13]), "+f"(d[14]), "+f"(d[15]), "+f"(d[16]), "+f"(d[17]), "+f"(d[18]), "+f"(d[19]), "+f"(d[20]), "+f"(d[21]), "+f"(d[22]), "+f"(d[23]), "+f"(d[24]), "+f"(d[25]), "+f"(d[26]), "+f"(d[27]), "+f"(d[28]), "+f"(d[29]), "+f"(d[30]), "+f"(d[31]), "+f"(d[32]), "+f"(d[33]), "+f"(d[34]), "+f"(d[35]), "+f"(d[36]), "+f"(d[37]), "+f"(d[38]), "+f"(d[39]), "+f"(d[40]), "+f"(d[41]), "+f"(d[42]), "+f"(d[43]), "+f"(d[44]), "+f"(d[45]), "+f"(d[46]), "+f"(d[47]), "+f"(d[48]), "+f"(d[49]), "+f"(d[50]), "+f"(d[51]), "+f"(d[52]), "+f"(d[53]), "+f"(d[54]), "+f"(d[55]), "+f"(d[56]), "+f"(d[57]), "+f"(d[58]), "+f"(d[59]), "+f"(d[60]), "+f"(d[61]), "+f"(d[62]), "+f"(d[63])
    : "r"(a[0]), "r"(a[1]), "r"(a[2]), "r"(a[3]), "r"(db_lo), "r"(db_hi), "r"(scale_d));
}
__device__ __forceinline__ void wgmma_ss_n160_bt(float (&d)[80], uint32_t da_lo, uint32_t da_hi, uint32_t db_lo, uint32_t db_hi, int scale_d) {
  asm volatile("{\n.reg .pred p;\n.reg .b64 da, db;\nsetp.ne.b32 p, %84, 0;\nmov.b64 da, {%80, %81};\nmov.b64 db, {%82, %83};\n"
    "wgmma.mma_async.sync.aligned.m64n160k16.f32.bf16.bf16 "
    "{%0, %1, %2, %3, %4, %5, %6, %7, %8, %9, %10, %11, %12, %13, %14, %15, %16, %17, %18, %19, %20, %21, %22, %23, %24, %25, %26, %27, %28, %29, %30, %31, %32, %33, %34, %35, %36, %37, %38, %39, %40, %41, %42, %43, %44, %45, %46, %47, %48, %49, %50, %51, %52, %53, %54, %55, %56, %57, %58, %59, %60, %61, %62, %63, %64, %65, %66, %67, %68, %69, %70, %71, %72, %73, %74, %75, %76, %77, %78, %79}, "
    "da, db, p, 1, 1, 0, 1;\n}\n"
    : "+f"(d[0]), "+f"(d[1]), "+f"(d[2]), "+f"(d[3]), "+f"(d[4]), "+f"(d[5]), "+f"(d[6]), "+f"(d[7]), "+f"(d[8]), "+f"(d[9]), "+f"(d[10]), "+f"(d[11]), "+f"(d[12]), "+f"(d[13]), "+f"(d[14]), "+f"(d[15]), "+f"(d[16]), "+f"(d[17]), "+f"(d[18]), "+f"(d[19]), "+f"(d[20]), "+f"(d[21]), "+f"(d[22]), "+f"(d[23]), "+f"(d[24]), "+f"(d[25]), "+f"(d[26]), "+f"(d[27]), "+f"(d[28]), "+f"(d[29]), "+f"(d[30]), "+f"(d[31]), "+f"(d[32]), "+f"(d[33]), "+f"(d[34]), "+f"(d[35]), "+f"(d[36]), "+f"(d[37]), "+f"(d[38]), "+f"(d[39]), "+f"(d[40]), "+f"(d[41]), "+f"(d[42]), "+f"(d[43]), "+f"(d[44]), "+f"(d[45]), "+f"(d[46]), "+f"(d[47]), "+f"(d[48]), "+f"(d[49]), "+f"(d[50]), "+f"(d[51]), "+f"(d[52]), "+f"(d[53]), "+f"(d[54]), "+f"(d[55]), "+f"(d[56]), "+f"(d[57]), "+f"(d[58]), "+f"(d[59]), "+f"(d[60]), "+f"(d[61]), "+f"(d[62]), "+f"(d[63]), "+f"(d[64]), "+f"(d[65]), "+f"(d[66]), "+f"(d[67]), "+f"(d[68]), "+f"(d[69]), "+f"(d[70]), "+f"(d[71]), "+f"(d[72]), "+f"(d[73]), "+f"(d[74]), "+f"(d[75]), "+f"(d[76]), "+f"(d[77]), "+f"(d[78]), "+f"(d[79])
    : "r"(da_lo), "r"(da_hi), "r"(db_lo), "r"(db_hi), "r"(scale_d));
}
__device__ __forceinline__ void wgmma_ss_n128_bt_init(float (&d)[64], uint32_t da_lo, uint32_t da_hi, uint32_t db_lo, uint32_t db_hi) {
  asm volatile("{\n.reg .pred p;\n.reg .b64 da, db;\nsetp.ne.b32 p, 0, 0;\nmov.b64 da, {%64, %65};\nmov.b64 db, {%66, %67};\n"
    "wgmma.mma_async.sync.aligned.m64n128k16.f32.bf16.bf16 "
    "{%0, %1, %2, %3, %4, %5, %6, %7, %8, %9, %10, %11, %12, %13, %14, %15, %16, %17, %18, %19, %20, %21, %22, %23, %24, %25, %26, %27, %28, %29, %30, %31, %32, %33, %34, %35, %36, %37, %38, %39, %40, %41, %42, %43, %44, %45, %46, %47, %48, %49, %50, %51, %52, %53, %54, %55, %56, %57, %58, %59, %60, %61, %62, %63}, "
    "da, db, p, 1, 1, 0, 1;\n}\n"
    : "=f"(d[0]), "=f"(d[1]), "=f"(d[2]), "=f"(d[3]), "=f"(d[4]), "=f"(d[5]), "=f"(d[6]), "=f"(d[7]), "=f"(d[8]), "=f"(d[9]), "=f"(d[10]), "=f"(d[11]), "=f"(d[12]), "=f"(d[13]), "=f"(d[14]), "=f"(d[15]), "=f"(d[16]), "=f"(d[17]), "=f"(d[18]), "=f"(d[19]), "=f"(d[20]), "=f"(d[21]), "=f"(d[22]), "=f"(d[23]), "=f"(d[24]), "=f"(d[25]), "=f"(d[26]), "=f"(d[27]), "=f"(d[28]), "=f"(d[29]), "=f"(d[30]), "=f"(d[31]), "=f"(d[32]), "=f"(d[33]), "=f"(d[34]), "=f"(d[35]), "=f"(d[36]), "=f"(d[37]), "=f"(d[38]), "=f"(d[39]), "=f"(d[40]), "=f"(d[41]), "=f"(d[42]), "=f"(d[43]), "=f"(d[44]), "=f"(d[45]), "=f"(d[46]), "=f"(d[47]), "=f"(d[48]), "=f"(d[49]), "=f"(d[50]), "=f"(d[51]), "=f"(d[52]), "=f"(d[53]), "=f"(d[54]), "=f"(d[55]), "=f"(d[56]), "=f"(d[57]), "=f"(d[58]), "=f"(d[59]), "=f"(d[60]), "=f"(d[61]), "=f"(d[62]), "=f"(d[63])
    : "r"(da_lo), "r"(da_hi), "r"(db_lo), "r"(db_hi));
}
__device__ __forceinline__ void wgmma_rs_n128_bn_init(float (&d)[64], const uint32_t (&a)[4], uint32_t db_lo, uint32_t db_hi) {
  asm volatile("{\n.reg .pred p;\n.reg .b64 db;\nsetp.ne.b32 p, 0, 0;\nmov.b64 db, {%68, %69};\n"
    "wgmma.mma_async.sync.aligned.m64n128k16.f32.bf16.bf16 "
    "{%0, %1, %2, %3, %4, %5, %6, %7, %8, %9, %10, %11, %12, %13, %14, %15, %16, %17, %18, %19, %20, %21, %22, %23, %24, %25, %26, %27, %28, %29, %30, %31, %32, %33, %34, %35, %36, %37, %38, %39, %40, %41, %42, %43, %44, %45, %46, %47, %48, %49, %50, %51, %52, %53, %54, %55, %56, %57, %58, %59, %60, %61, %62, %63}, "
    "{%64, %65, %66, %67}, db, p, 1, 1, 0;\n}\n"
    : "=f"(d[0]), "=f"(d[1]), "=f"(d[2]), "=f"(d[3]), "=f"(d[4]), "=f"(d[5]), "=f"(d[6]), "=f"(d[7]), "=f"(d[8]), "=f"(d[9]), "=f"(d[10]), "=f"(d[11]), "=f"(d[12]), "=f"(d[13]), "=f"(d[14]), "=f"(d[15]), "=f"(d[16]), "=f"(d[17]), "=f"(d[18]), "=f"(d[19]), "=f"(d[20]), "=f"(d[21]), "=f"(d[22]), "=f"(d[23]), "=f"(d[24]), "=f"(d[25]), "=f"(d[26]), "=f"(d[27]), "=f"(d[28]), "=f"(d[29]), "=f"(d[30]), "=f"(d[31]), "=f"(d[32]), "=f"(d[33]), "=f"(d[34]), "=f"(d[35]), "=f"(d[36]), "=f"(d[37]), "=f"(d[38]), "=f"(d[39]), "=f"(d[40]), "=f"(d[41]), "=f"(d[42]), "=f"(d[43]), "=f"(d[44]), "=f"(d[45]), "=f"(d[46]), "=f"(d[47]), "=f"(d[48]), "=f"(d[49]), "=f"(d[50]), "=f"(d[51]), "=f"(d[52]), "=f"(d[53]), "=f"(d[54]), "=f"(d[55]), "=f"(d[56]), "=f"(d[57]), "=f"(d[58]), "=f"(d[59]), "=f"(d[60]), "=f"(d[61]), "=f"(d[62]), "=f"(d[63])
    : "r"(a[0]), "r"(a[1]), "r"(a[2]), "r"(a[3]), "r"(db_lo), "r"(db_hi));
}
__device__ __forceinline__ void wgmma_ss_n160_bt_init(float (&d)[80], uint32_t da_lo, uint32_t da_hi, uint32_t db_lo, uint32_t db_hi) {
  asm volatile("{\n.reg .pred p;\n.reg .b64 da, db;\nsetp.ne.b32 p, 0, 0;\nmov.b64 da, {%80, %81};\nmov.b64 db, {%82, %83};\n"
    "wgmma.mma_async.sync.aligned.m64n160k16.f32.bf16.bf16 "
    "{%0, %1, %2, %3, %4, %5, %6, %7, %8, %9, %10, %11, %12, %13, %14, %15, %16, %17, %18, %19, %20, %21, %22, %23, %24, %25, %26, %27, %28, %29, %30, %31, %32, %33, %34, %35, %36, %37, %38, %39, %40, %41, %42, %43, %44, %45, %46, %47, %48, %49, %50, %51, %52, %53, %54, %55, %56, %57, %58, %59, %60, %61, %62, %63, %64, %65, %66, %67, %68, %69, %70, %71, %72, %73, %74, %75, %76, %77, %78, %79}, "
    "da, db, p, 1, 1, 0, 1;\n}\n"
    : "=f"(d[0]), "=f"(d[1]), "=f"(d[2]), "=f"(d[3]), "=f"(d[4]), "=f"(d[5]), "=f"(d[6]), "=f"(d[7]), "=f"(d[8]), "=f"(d[9]), "=f"(d[10]), "=f"(d[11]), "=f"(d[12]), "=f"(d[13]), "=f"(d[14]), "=f"(d[15]), "=f"(d[16]), "=f"(d[17]), "=f"(d[18]), "=f"(d[19]), "=f"(d[20]), "=f"(d[21]), "=f"(d[22]), "=f"(d[23]), "=f"(d[24]), "=f"(d[25]), "=f"(d[26]), "=f"(d[27]), "=f"(d[28]), "=f"(d[29]), "=f"(d[30]), "=f"(d[31]), "=f"(d[32]), "=f"(d[33]), "=f"(d[34]), "=f"(d[35]), "=f"(d[36]), "=f"(d[37]), "=f"(d[38]), "=f"(d[39]), "=f"(d[40]), "=f"(d[41]), "=f"(d[42]), "=f"(d[43]), "=f"(d[44]), "=f"(d[45]), "=f"(d[46]), "=f"(d[47]), "=f"(d[48]), "=f"(d[49]), "=f"(d[50]), "=f"(d[51]), "=f"(d[52]), "=f"(d[53]), "=f"(d[54]), "=f"(d[55]), "=f"(d[56]), "=f"(d[57]), "=f"(d[58]), "=f"(d[59]), "=f"(d[60]), "=f"(d[61]), "=f"(d[62]), "=f"(d[63]), "=f"(d[64]), "=f"(d[65]), "=f"(d[66]), "=f"(d[67]), "=f"(d[68]), "=f"(d[69]), "=f"(d[70]), "=f"(d[71]), "=f"(d[72]), "=f"(d[73]), "=f"(d[74]), "=f"(d[75]), "=f"(d[76]), "=f"(d[77]), "=f"(d[78]), "=f"(d[79])
    : "r"(da_lo), "r"(da_hi), "r"(db_lo), "r"(db_hi));
}
__device__ __forceinline__ void wgmma_rs_n128_bt(float (&d)[64], const uint32_t (&a)[4], uint32_t db_lo, uint32_t db_hi, int scale_d) {
  asm volatile("{\n.reg .pred p;\n.reg .b64 db;\nsetp.ne.b32 p, %70, 0;\nmov.b64 db, {%68, %69};\n"
    "wgmma.mma_async.sync.aligned.m64n128k16.f32.bf16.bf16 "
    "{%0, %1, %2, %3, %4, %5, %6, %7, %8, %9, %10, %11, %12, %13, %14, %15, %16, %17, %18, %19, %20, %21, %22, %23, %24, %25, %26, %27, %28, %29, %30, %31, %32, %33, %34, %35, %36, %37, %38, %39, %40, %41, %42, %43, %44, %45, %46, %47, %48, %49, %50, %51, %52, %53, %54, %55, %56, %57, %58, %59, %60, %61, %62, %63}, "
    "{%64, %65, %66, %67}, db, p, 1, 1, 1;\n}\n"
    : "+f"(d[0]), "+f"(d[1]), "+f"(d[2]), "+f"(d[3]), "+f"(d[4]), "+f"(d[5]), "+f"(d[6]), "+f"(d[7]), "+f"(d[8]), "+f"(d[9]), "+f"(d[10]), "+f"(d[11]), "+f"(d[12]), "+f"(d[13]), "+f"(d[14]), "+f"(d[15]), "+f"(d[16]), "+f"(d[17]), "+f"(d[18]), "+f"(d[19]), "+f"(d[20]), "+f"(d[21]), "+f"(d[22]), "+f"(d[23]), "+f"(d[24]), "+f"(d[25]), "+f"(d[26]), "+f"(d[27]), "+f"(d[28]), "+f"(d[29]), "+f"(d[30]), "+f"(d[31]), "+f"(d[32]), "+f"(d[33]), "+f"(d[34]), "+f"(d[35]), "+f"(d[36]), "+f"(d[37]), "+f"(d[38]), "+f"(d[39]), "+f"(d[40]), "+f"(d[41]), "+f"(d[42]), "+f"(d[43]), "+f"(d[44]), "+f"(d[45]), "+f"(d[46]), "+f"(d[47]), "+f"(d[48]), "+f"(d[49]), "+f"(d[50]), "+f"(d[51]), "+f"(d[52]), "+f"(d[53]), "+f"(d[54]), "+f"(d[55]), "+f"(d[56]), "+f"(d[57]), "+f"(d[58]), "+f"(d[59]), "+f"(d[60]), "+f"(d[61]), "+f"(d[62]), "+f"(d[63])
    : "r"(a[0]), "r"(a[1]), "r"(a[2]), "r"(a[3]), "r"(db_lo), "r"(db_hi), "r"(scale_d));
}
__device__ __forceinline__ void wgmma_rs_n160_bt(float (&d)[80], const uint32_t (&a)[4], uint32_t db_lo, uint32_t db_hi, int scale_d) {
  asm volatile("{\n.reg .pred p;\n.reg .b64 db;\nsetp.ne.b32 p, %86, 0;\nmov.b64 db, {%84, %85};\n"
    "wgmma.mma_async.sync.aligned.m64n160k16.f32.bf16.bf16 "
    "{%0, %1, %2, %3, %4, %5, %6, %7, %8, %9, %10, %11, %12, %13, %14, %15, %16, %17, %18, %19, %20, %21, %22, %23, %24, %25, %26, %27, %28, %29, %30, %31, %32, %33, %34, %35, %36, %37, %38, %39, %40, %41, %42, %43, %44, %45, %46, %47, %48, %49, %50, %51, %52, %53, %54, %55, %56, %57, %58, %59, %60, %61, %62, %63, %64, %65, %66, %67, %68, %69, %70, %71, %72, %73, %74, %75, %76, %77, %78, %79}, "
    "{%80, %81, %82, %83}, db, p, 1, 1, 1;\n}\n"
    : "+f"(d[0]), "+f"(d[1]), "+f"(d[2]), "+f"(d[3]), "+f"(d[4]), "+f"(d[5]), "+f"(d[6]), "+f"(d[7]), "+f"(d[8]), "+f"(d[9]), "+f"(d[10]), "+f"(d[11]), "+f"(d[12]), "+f"(d[13]), "+f"(d[14]), "+f"(d[15]), "+f"(d[16]), "+f"(d[17]), "+f"(d[18]), "+f"(d[19]), "+f"(d[20]), "+f"(d[21]), "+f"(d[22]), "+f"(d[23]), "+f"(d[24]), "+f"(d[25]), "+f"(d[26]), "+f"(d[27]), "+f"(d[28]), "+f"(d[29]), "+f"(d[30]), "+f"(d[31]), "+f"(d[32]), "+f"(d[33]), "+f"(d[34]), "+f"(d[35]), "+f"(d[36]), "+f"(d[37]), "+f"(d[38]), "+f"(d[39]), "+f"(d[40]), "+f"(d[41]), "+f"(d[42]), "+f"(d[43]), "+f"(d[44]), "+f"(d[45]), "+f"(d[46]), "+f"(d[47]), "+f"(d[48]), "+f"(d[49]), "+f"(d[50]), "+f"(d[51]), "+f"(d[52]), "+f"(d[53]), "+f"(d[54]), "+f"(d[55]), "+f"(d[56]), "+f"(d[57]), "+f"(d[58]), "+f"(d[59]), "+f"(d[60]), "+f"(d[61]), "+f"(d[62]), "+f"(d[63]), "+f"(d[64]), "+f"(d[65]), "+f"(d[66]), "+f"(d[67]), "+f"(d[68]), "+f"(d[69]), "+f"(d[70]), "+f"(d[71]), "+f"(d[72]), "+f"(d[73]), "+f"(d[74]), "+f"(d[75]), "+f"(d[76]), "+f"(d[77]), "+f"(d[78]), "+f"(d[79])
    : "r"(a[0]), "r"(a[1]), "r"(a[2]), "r"(a[3]), "r"(db_lo), "r"(db_hi), "r"(scale_d));
}

__device__ __forceinline__ uint32_t t4_off(uint32_t s) {
  return s == 0 ? 110592u : (s == 1 ? 192512u : (s == 5 ? 147456u : (s - 2) * T4_STAGE));
}
__device__ __forceinline__ uint32_t slot_addr(uint32_t sb, uint32_t s) { return sb + s * SLOT + (s >= 6 ? 49152u : 0u); }

struct Ctx {
  uint32_t sb;
  uint32_t sd;
  uint32_t bars;
  uint32_t fullph;
  uint32_t slot;
  int w;
  int tid;
  uint32_t rank;
};

__device__ __forceinline__ void release_slot(const Ctx& c, uint32_t s, int warp_in_wg = 0) {
  if (c.tid == warp_in_wg * 32) mbar_arrive_both(c.bars + 8 * (B_EMPTY + s));
}
__device__ __forceinline__ uint32_t acquire_slot(Ctx& c, uint32_t mask) {
  uint32_t s = c.slot;
  mbar_wait(c.bars + 8 * (B_FULL + s), (c.fullph >> s) & 1);
  c.fullph ^= (1u << s);
  c.slot = (s + 1) & mask;
  return s;
}

__device__ __forceinline__ void pack_frags(const float (&s)[64], uint32_t (&f)[8][4]) {
#pragma unroll
  for (int k = 0; k < 8; k++) {
    f[k][0] = pack_bf16(s[8 * k + 0], s[8 * k + 1]);
    f[k][1] = pack_bf16(s[8 * k + 2], s[8 * k + 3]);
    f[k][2] = pack_bf16(s[8 * k + 4], s[8 * k + 5]);
    f[k][3] = pack_bf16(s[8 * k + 6], s[8 * k + 7]);
  }
}
__device__ __forceinline__ void swiglu_slice(const uint32_t (&f)[8][4], int j, uint8_t* dst) {
  const uint32_t g01 = f[j >> 1][(j & 1) * 2], g23 = f[j >> 1][(j & 1) * 2 + 1];
  const uint32_t u01 = f[4 + (j >> 1)][(j & 1) * 2], u23 = f[4 + (j >> 1)][(j & 1) * 2 + 1];
  const uint32_t s01 = silu_pair(g01), s23 = silu_pair(g23);
  const uint32_t h01 = mul_bf16x2(s01, u01), h23 = mul_bf16x2(s23, u23);
  st_global_u32(dst + j * 128, h01);
  st_global_u32(dst + j * 128 + 1024, h23);
}

__device__ __forceinline__ void pass_gemm_prev(Ctx& c, float (&acc)[64], const uint32_t (&prev)[8][4], bool has_prev, uint8_t* prev_dst, bool first, uint32_t xph) {
  uint32_t a_lo = ((c.sd + XN_OFF + c.w * XN_WG) >> 4) | desc_lo_lbo(16);
  uint32_t prev_slot = 0;
#pragma unroll
  for (int kb = 0; kb < KB_D; kb++) {
    if (first) mbar_wait(c.bars + 8 * (B_XFULL + kb), xph);
    uint32_t s = acquire_slot(c, 3);
    uint32_t b_lo = ((c.sd + s * SLOT) >> 4) | desc_lo_lbo(8192);
    asm volatile("" : "+r"(a_lo));
    if (kb > 0) reg_fence(acc);
    wg_fence();
    if (kb == 0) wgmma_ss_n128_bt_init(acc, a_lo, HI_SW128, b_lo, HI_SW128);
    else         wgmma_ss_n128_bt(acc, a_lo, HI_SW128, b_lo, HI_SW128, 1);
#pragma unroll
    for (int kk = 1; kk < 4; kk++)
      wgmma_ss_n128_bt(acc, a_lo + kk * 2, HI_SW128, b_lo + kk * 128, HI_SW128, 1);
    wg_commit();
    a_lo += 512;
    if (kb >= 1 && kb <= 8) { if (has_prev) swiglu_slice(prev, kb - 1, prev_dst); }
    if (kb > 0) { wg_wait<1>(); release_slot(c, prev_slot, kb & 3); }
    prev_slot = s;
  }
  wg_wait<0>();
  reg_fence(acc);
  release_slot(c, prev_slot);
}
__device__ __forceinline__ void pass_gemm_plain(Ctx& c, float (&acc)[64], bool early_dead) {
  uint32_t a_lo = ((c.sd + XN_OFF + c.w * XN_WG) >> 4) | desc_lo_lbo(16);
  uint32_t prev_slot = 0;
#pragma unroll
  for (int kb = 0; kb < KB_D; kb++) {
    uint32_t s = acquire_slot(c, 3);
    uint32_t b_lo = ((c.sd + s * SLOT) >> 4) | desc_lo_lbo(8192);
    asm volatile("" : "+r"(a_lo));
    if (kb > 0) reg_fence(acc);
    wg_fence();
    if (kb == 0) wgmma_ss_n128_bt_init(acc, a_lo, HI_SW128, b_lo, HI_SW128);
    else         wgmma_ss_n128_bt(acc, a_lo, HI_SW128, b_lo, HI_SW128, 1);
#pragma unroll
    for (int kk = 1; kk < 4; kk++)
      wgmma_ss_n128_bt(acc, a_lo + kk * 2, HI_SW128, b_lo + kk * 128, HI_SW128, 1);
    wg_commit();
    a_lo += 512;
    if (kb > 0) { wg_wait<1>(); release_slot(c, prev_slot, kb & 3); }
    if (kb == 4 && early_dead && c.tid == 0) mbar_arrive_both(c.bars + 8 * B_XDEAD);
    prev_slot = s;
  }
  wg_wait<0>();
  reg_fence(acc);
  release_slot(c, prev_slot);
}

__device__ __forceinline__ void signal_event(const Ctx& c) {
  mbar_arrive(c.bars + 8 * (B_SIG + c.w));
}

struct SmState { float n0, n1, t0, t1, l0, l1, al0, al1; };
__device__ __forceinline__ void row_max_f(const float (&s)[64], float& x0, float& x1) {
  float a0 = fmaxf(s[0], s[1]), a1 = fmaxf(s[4], s[5]), b0 = fmaxf(s[2], s[3]), b1 = fmaxf(s[6], s[7]);
#pragma unroll
  for (int j = 2; j < 16; j += 2) {
    a0 = fmaxf(a0, fmaxf(s[4 * j], s[4 * j + 1]));     b0 = fmaxf(b0, fmaxf(s[4 * j + 2], s[4 * j + 3]));
    a1 = fmaxf(a1, fmaxf(s[4 * j + 4], s[4 * j + 5])); b1 = fmaxf(b1, fmaxf(s[4 * j + 6], s[4 * j + 7]));
  }
  x0 = fmaxf(a0, a1); x1 = fmaxf(b0, b1);
}
__device__ __forceinline__ bool softmax_ref(const float (&s)[64], bool first, SmState& st) {
  int a0 = __float_as_int(s[0]), a1 = __float_as_int(s[4]), b0 = __float_as_int(s[2]), b1 = __float_as_int(s[6]);
  a0 = max(a0, __float_as_int(s[1])); a1 = max(a1, __float_as_int(s[5])); b0 = max(b0, __float_as_int(s[3])); b1 = max(b1, __float_as_int(s[7]));
#pragma unroll
  for (int j = 2; j < 16; j += 2) {
    a0 = __vimax3_s32(a0, __float_as_int(s[4 * j]), __float_as_int(s[4 * j + 1]));
    b0 = __vimax3_s32(b0, __float_as_int(s[4 * j + 2]), __float_as_int(s[4 * j + 3]));
    a1 = __vimax3_s32(a1, __float_as_int(s[4 * j + 4]), __float_as_int(s[4 * j + 5]));
    b1 = __vimax3_s32(b1, __float_as_int(s[4 * j + 6]), __float_as_int(s[4 * j + 7]));
  }
  int i0 = max(a0, a1), i1 = max(b0, b1);
  float x0 = __int_as_float(i0), x1 = __int_as_float(i1);
  const bool need = first || !(x0 <= st.t0) || !(x1 <= st.t1) || st.t0 < 0.f || st.t1 < 0.f;
  if (!__any_sync(0xffffffffu, need)) return false;
  i0 = max(i0, __shfl_xor_sync(0xffffffffu, i0, 1));
  i1 = max(i1, __shfl_xor_sync(0xffffffffu, i1, 1));
  i0 = max(i0, __shfl_xor_sync(0xffffffffu, i0, 2));
  i1 = max(i1, __shfl_xor_sync(0xffffffffu, i1, 2));
  x0 = __int_as_float(i0); x1 = __int_as_float(i1);
  if (__any_sync(0xffffffffu, (i0 | i1) < 0)) {
    row_max_f(s, x0, x1);
    x0 = fmaxf(x0, __shfl_xor_sync(0xffffffffu, x0, 1));
    x1 = fmaxf(x1, __shfl_xor_sync(0xffffffffu, x1, 1));
    x0 = fmaxf(x0, __shfl_xor_sync(0xffffffffu, x0, 2));
    x1 = fmaxf(x1, __shfl_xor_sync(0xffffffffu, x1, 2));
  }
  float n0 = -x0 * SM_SCALE, n1 = -x1 * SM_SCALE;
  if (first) {
    st.l0 = 0.f; st.l1 = 0.f;
  } else {
    n0 = fminf(n0, st.n0); n1 = fminf(n1, st.n1);
    st.al0 = ex2(n0 - st.n0); st.al1 = ex2(n1 - st.n1);
    st.l0 *= st.al0; st.l1 *= st.al1;
  }
  st.n0 = n0; st.n1 = n1;
  st.t0 = fmaf(n0, -1.0f / SM_SCALE, SM_LAZY / SM_SCALE); st.t1 = fmaf(n1, -1.0f / SM_SCALE, SM_LAZY / SM_SCALE);
  return !first;
}
__device__ __forceinline__ void softmax_exp(float (&s)[64], SmState& st) {
#pragma unroll
  for (int j = 0; j < 16; j++) {
    s[4 * j + 0] = ex2(fmaf(s[4 * j + 0], SM_SCALE, st.n0)); s[4 * j + 1] = ex2(fmaf(s[4 * j + 1], SM_SCALE, st.n0));
    s[4 * j + 2] = ex2(fmaf(s[4 * j + 2], SM_SCALE, st.n1)); s[4 * j + 3] = ex2(fmaf(s[4 * j + 3], SM_SCALE, st.n1));
  }
  float r0 = s[0] + s[1], r2 = s[2] + s[3];
#pragma unroll
  for (int j = 1; j < 16; j++) { r0 += s[4 * j + 0] + s[4 * j + 1]; r2 += s[4 * j + 2] + s[4 * j + 3]; }
  st.l0 += r0;
  st.l1 += r2;
}
__device__ __forceinline__ uint32_t peek_dslot(const Ctx& c, uint32_t ahead) {
  const uint32_t s = (c.slot + 2 * ahead) & 7;
  return mbar_test(c.bars + 8 * (B_FULL + s), (c.fullph >> s) & 1);
}
__device__ __forceinline__ uint32_t acquire_dslot(Ctx& c, uint32_t tok) {
  uint32_t s = c.slot;
  mbar_wait_tok(c.bars + 8 * (B_FULL + s), (c.fullph >> s) & 1, tok);
  c.fullph ^= (1u << s);
  c.slot = (s + 2) & 7;
  return s;
}
__device__ __forceinline__ void release_dslot(const Ctx& c, uint32_t s, int warp_in_wg) {
  if (c.tid == warp_in_wg * 32) mbar_arrive_both(c.bars + 8 * (B_EMPTY + s));
}
__device__ __forceinline__ uint32_t issue_qk(Ctx& c, float (&s)[64], const uint32_t (&q)[8][4], uint32_t tok) {
  const uint32_t sl = acquire_dslot(c, tok);
  const uint32_t lo = (slot_addr(c.sd, sl) >> 4) | desc_lo_lbo(16);
  wg_fence();
  wgmma_rs_n128_bn_init(s, q[0], lo, HI_SW128);
#pragma unroll
  for (int kk = 1; kk < 8; kk++) wgmma_rs_n128_bn(s, q[kk], lo + (kk >> 2) * 1024 + (kk & 3) * 2, HI_SW128, 1);
  wg_commit();
  return sl;
}
__device__ __forceinline__ uint32_t issue_pv(Ctx& c, float (&o)[64], const uint32_t (&p)[8][4], int accumulate, uint32_t tok) {
  const uint32_t sl = acquire_dslot(c, tok);
  const uint32_t lo = (slot_addr(c.sd, sl) >> 4) | desc_lo_lbo(8192);
  wg_fence();
  wgmma_rs_n128_bt(o, p[0], lo, HI_SW128, accumulate);
#pragma unroll
  for (int kk = 1; kk < 8; kk++) wgmma_rs_n128_bt(o, p[kk], lo + kk * 128 + (kk >> 2) * 512, HI_SW128, 1);
  wg_commit();
  return sl;
}
__device__ __forceinline__ void row_norm(float l0, float l1, float& i0, float& i1) {
  l0 += __shfl_xor_sync(0xffffffffu, l0, 1);
  l1 += __shfl_xor_sync(0xffffffffu, l1, 1);
  l0 += __shfl_xor_sync(0xffffffffu, l0, 2);
  l1 += __shfl_xor_sync(0xffffffffu, l1, 2);
  i0 = __fdividef(1.0f, l0); i1 = __fdividef(1.0f, l1);
}
__device__ __forceinline__ void store_o_direct(const Ctx& c, const float (&o)[64], float l0, float l1, uint8_t* dst  ) {
  float i0, i1;
  row_norm(l0, l1, i0, i1);
#pragma unroll
  for (int j = 0; j < 16; j++) {
    uint8_t* d = dst + (j >> 3) * 16384 + (j & 7) * 128;
    st_global_u32(d, pack_bf16(o[4 * j] * i0, o[4 * j + 1] * i0));
    st_global_u32(d + 1024, pack_bf16(o[4 * j + 2] * i1, o[4 * j + 3] * i1));
  }
  signal_event(c);
}
__device__ __forceinline__ void store_o_staged(const Ctx& c, const float (&o)[64], float l0, float l1, uint32_t addr  ) {
  float i0, i1;
  row_norm(l0, l1, i0, i1);
#pragma unroll
  for (int k = 0; k < 8; k++) {
    const uint32_t r0 = pack_bf16(o[8 * k + 0] * i0, o[8 * k + 1] * i0), r1 = pack_bf16(o[8 * k + 2] * i1, o[8 * k + 3] * i1);
    const uint32_t r2 = pack_bf16(o[8 * k + 4] * i0, o[8 * k + 5] * i0), r3 = pack_bf16(o[8 * k + 6] * i1, o[8 * k + 7] * i1);
    asm volatile("stmatrix.sync.aligned.m8n8.x4.shared.b16 [%0], {%1,%2,%3,%4};" :: "r"(addr + (k >> 2) * 8192 + (k & 3) * 256), "r"(r0), "r"(r1), "r"(r2), "r"(r3) : "memory");
  }
  asm volatile("fence.proxy.async.shared::cta;" ::: "memory");
  signal_event(c);
}

__device__ __forceinline__ void attention4(Ctx& c, uint32_t (&q)[8][4], uint8_t* o_all, int m, int head0) {
  float s[64], o[64];
  uint32_t p[8][4];
  SmState st;
  st.n0 = 0.f; st.n1 = 0.f; st.t0 = 0.f; st.t1 = 0.f; st.l0 = 0.f; st.l1 = 0.f; st.al0 = 1.f; st.al1 = 1.f;
#pragma unroll
  for (int i = 0; i < 64; i++) o[i] = 0.f;
  const int my_turn = 1 + c.w, other_turn = 2 - c.w;
  const uint32_t thr_off = c.w * 8192 + (c.tid >> 5) * 2048 + (c.tid & 31) * 4;
  uint8_t* obase = o_all + ((size_t)m * 64 + head0 * 2) * 16384 + thr_off;
  const uint32_t stash_w = c.sb + XN_OFF + c.w * XN_WG + STASH_OFF + (c.tid >> 5) * 2048;
  const uint32_t lane = c.tid & 31;
  if (c.w == 1) bar_arrive(1, 256);
  bar_sync(my_turn, 256);
  const uint32_t slot_p1 = c.slot;
  c.slot = 4;
  uint32_t ks = issue_qk(c, s, q, 0), vs;
  bar_arrive(other_turn, 256);
  wg_wait<0>();
  reg_fence(s);
  release_dslot(c, ks, 1);
  softmax_ref(s, true, st);
  uint32_t ktok = peek_dslot(c, 0), vtok = peek_dslot(c, 1);
  softmax_exp(s, st);
  pack_frags(s, p);
  float lf0 = 0.f, lf1 = 0.f;
#pragma unroll 1
  for (int i = 0; i < 15; i++) {
    const int jn = (i + 1) & 3;
    bar_sync(my_turn, 256);
    reg_fence(o); reg_fence_u(p); reg_fence_u(q);
    ks = issue_qk(c, s, q, ktok);
    if ((i & 3) == 0 && i > 0) {
      store_o_staged(c, o, lf0, lf1, stash_w + ((i >> 2) - 1) * 16384 + (lane & 7) * 16 + ((lane >> 3) & 1) * 1024 + (lane >> 4) * 128);
      reg_fence(o);
    }
    vs = issue_pv(c, o, p, (i & 3) != 0, vtok);
    bar_arrive(other_turn, 256);
    wg_wait<1>();
    reg_fence(s); reg_fence_u(q);
    if (jn == 0) { lf0 = st.l0; lf1 = st.l1; }
    if (jn == 3 && i < 12) {
      const uint32_t a = stash_w + ((i + 1) >> 2) * 16384 + lane * 16;
#pragma unroll
      for (int k = 0; k < 8; k++)
        asm volatile("ld.shared.v4.u32 {%0,%1,%2,%3}, [%4];" : "=r"(q[k][0]), "=r"(q[k][1]), "=r"(q[k][2]), "=r"(q[k][3]) : "r"(a + (k >> 2) * 8192 + (k & 3) * 512) : "memory");
    }
    const bool resc = softmax_ref(s, jn == 0, st);
    release_dslot(c, ks, 1);
    ktok = peek_dslot(c, 0);
    vtok = peek_dslot(c, 1);
    softmax_exp(s, st);
    wg_wait<0>();
    reg_fence(o); reg_fence_u(p);
    release_dslot(c, vs, 2);
    if (resc) {
#pragma unroll
      for (int j = 0; j < 16; j++) { o[4 * j] *= st.al0; o[4 * j + 1] *= st.al0; o[4 * j + 2] *= st.al1; o[4 * j + 3] *= st.al1; }
    }
    pack_frags(s, p);
    reg_fence_u(p);
  }
  bar_sync(my_turn, 256);
  reg_fence(o); reg_fence_u(p);
  vs = issue_pv(c, o, p, 1, ktok);
  if (c.w == 0) bar_arrive(other_turn, 256);
  wg_wait<0>();
  reg_fence(o);
  release_dslot(c, vs, 2);
  c.slot = slot_p1;
  if (c.tid == 0) mbar_arrive_both(c.bars + 8 * B_ADONE);
  store_o_direct(c, o, st.l0, st.l1, obase + (size_t)3 * 32768);
}

__device__ __forceinline__ void teardown(unsigned int* done_ctr) {
  __syncwarp();
  asm volatile("barrier.cluster.arrive.relaxed.aligned;\nbarrier.cluster.wait.aligned;" ::: "memory");
  if (threadIdx.x == 0) asm volatile("red.relaxed.gpu.global.add.u32 [%0], 1;" :: "l"(done_ctr) : "memory");
}

__global__ void __cluster_dims__(2, 1, 1) __launch_bounds__(384, 1)
fused_kernel(const __grid_constant__ CUtensorMap map_wq, const __grid_constant__ CUtensorMap map_w1, const __grid_constant__ CUtensorMap map_w3,
             const __grid_constant__ CUtensorMap map_k, const __grid_constant__ CUtensorMap map_v,
             const __grid_constant__ CUtensorMap map_wo, const __grid_constant__ CUtensorMap map_w2,
             const __grid_constant__ Params prm) {
  extern __shared__ __align__(1024) uint8_t smem[];
  const uint32_t sb = smem_u32(smem);
  const uint32_t bars = sb + BAR_OFF;
  const int warp = __shfl_sync(0xffffffffu, (int)(threadIdx.x >> 5), 0), lane = threadIdx.x & 31;
  const uint32_t rank = blockIdx.x & 1;
  const int pair = blockIdx.x >> 1;
  const PairSched& sch = prm.sched[pair];

  if (warp == 0) {
    if (sb & 1023) asm volatile("trap;");
    for (int i = lane; i < B_COUNT; i += 32) {
      uint32_t cnt = 1;
      if ((i >= B_EMPTY && i < B_XFULL) || i == B_XDEAD || (i >= B_EMPTY4 && i < B_SIG)) cnt = 4;
      if (i == B_ADONE) cnt = 8;
      if (i == B_SIG || i == B_SIG + 1) cnt = 128;
      if (i == B_SFREE) cnt = 4;
      mbar_init(bars + 8 * i, cnt);
    }
    asm volatile("fence.mbarrier_init.release.cluster;" ::: "memory");
    __syncwarp();
  } else if (threadIdx.x == 32) {
    const CUtensorMap* maps[5] = {&map_w1, &map_w3, &map_wq, &map_k, &map_v};
#pragma unroll
    for (int i = 0; i < 5; i++) asm volatile("prefetch.tensormap [%0];" :: "l"(maps[i]) : "memory");
  }
  __syncwarp();
  asm volatile("barrier.cluster.arrive.relaxed.aligned;" ::: "memory");
  unsigned int done = 0;
  if (warp == 0 || warp == 3) asm volatile("ld.relaxed.gpu.global.u32 %0, [%1];" : "=r"(done) : "l"(prm.done) : "memory");

  if (warp < 4) {
    asm volatile("setmaxnreg.dec.sync.aligned.u32 40;");
    if (warp == 3 && sch.nseg > 0) {
      if (lane == 0) flag_wait_spin(&prm.cnt_xn[(2 * sch.seg[0].p + rank) * 32], (done / gridDim.x + 1) * 8);
      __syncwarp();
    }
    asm volatile("barrier.cluster.wait.acquire.aligned;" ::: "memory");
    if (warp == 0) {
      const bool leader = elect_one();
      const unsigned int ep1 = done / gridDim.x + 1;
      uint32_t eph = 0xFFu;
      uint32_t slot = 0;
      uint32_t xdead_ph = 0, adone_ph = 0;
      bool xn_busy = false, ring_hi_busy = false;
#pragma unroll 1
      for (int sg = 0; sg < sch.nseg; sg++) {
        const Seg seg = sch.seg[sg];
        if (ring_hi_busy) { adone_ph ^= 1; ring_hi_busy = false; } else if (xn_busy) { xdead_ph ^= 1; }
        xn_busy = true;
        const int npass = seg.nc + (seg.head0 != 0xFF ? 4 : 0);
#pragma unroll 1
        for (int ps = 0; ps < npass; ps++) {
          const CUtensorMap* mp; int col;
          if (ps < seg.nc) { mp = rank ? &map_w3 : &map_w1; col = (seg.c0 + ps) * 64; }
          else { mp = &map_wq; col = (seg.head0 + ((ps - seg.nc + 1) & 3)) * 128 + rank * 64; }
#pragma unroll 1
          for (int kb = 0; kb < KB_D; kb++) {
            const uint32_t s = slot;
            mbar_wait(bars + 8 * (B_EMPTY + s), (eph >> s) & 1);
            eph ^= (1u << s);
            slot = (s + 1) & 3;
            if (leader) {
              mbar_expect_tx(bars + 8 * (B_FULL + s), SLOT);
              tma_2d_mc(sb + s * SLOT + rank * 8192, mp, bars + 8 * (B_FULL + s), col, kb * 64);
            }
          }
        }
        if (seg.head0 != 0xFF) {
          const uint32_t slot_p1 = slot;
          slot = 4;
          mbar_wait(bars + 8 * B_XDEAD, xdead_ph); xdead_ph ^= 1;
#pragma unroll 1
          for (int it = 0; it < 32; it++) {
            const bool isk = (it == 0) || ((it & 1) && it < 31);
            const int blk = it == 0 ? 0 : (it == 31 ? 15 : ((it & 1) ? (it + 1) >> 1 : (it >> 1) - 1));
            const int row0 = (seg.head0 + (blk >> 2)) * SK + (SK - WIN) + (blk & 3) * 128;
            if (it == 2 || it == 3) mbar_wait(bars + 8 * (B_EMPTY + slot + 1), (eph >> (slot + 1)) & 1);
            const uint32_t s = slot;
            mbar_wait(bars + 8 * (B_EMPTY + s), (eph >> s) & 1);
            eph ^= (1u << s);
            slot = (s + 2) & 7;
            if (leader) {
              const uint32_t fb = bars + 8 * (B_FULL + s), dst = slot_addr(sb, s) + rank * 8192;
              mbar_expect_tx(fb, 2 * SLOT);
              if (isk) { tma_2d_mc(dst, &map_k, fb, 0, row0 + rank * 64); tma_2d_mc(dst + SLOT, &map_k, fb, 64, row0 + rank * 64); }
              else     { tma_2d_mc(dst, &map_v, fb, rank * 64, row0); tma_2d_mc(dst + SLOT, &map_v, fb, rank * 64, row0 + 64); }
            }
          }
          slot = slot_p1;
          xn_busy = false;
          ring_hi_busy = true;
        }
      }
      if (sch.nt4 > 0) {
        if (leader) {
          asm volatile("prefetch.tensormap [%0];" :: "l"(&map_wo) : "memory");
          asm volatile("prefetch.tensormap [%0];" :: "l"(&map_w2) : "memory");
        }
        uint32_t s4 = 0, e4ph = 0x3Fu, cnt = 0;
        bool smem_free = false;
#pragma unroll 1
        for (int t = 0; t < sch.nt4; t++) {
          const T4Task tk = sch.t4[t];
          const int m = 2 * tk.p + rank;
          const int nkb = tk.type ? 64 : NCHUNK;
          const unsigned int* fp = tk.type ? &prm.cnt_o[m * NHEAD + prm.head_order[lane]] : &prm.cnt_h[m * 32];
          const unsigned int target = tk.type ? ep1 * 2 : ep1 * (2 * NCHUNK);
          uint32_t ready = poll_flags(fp, target);
          const uint8_t* abase = tk.type ? prm.o + (size_t)m * 64 * 16384 : prm.h + (size_t)m * NCHUNK * 16384;
          const CUtensorMap* mp = tk.type ? &map_wo : &map_w2;
#pragma unroll 1
          for (int k = 0; k < nkb; k++) {
            const int dep = tk.type ? (k >> 1) : 0;
            if (!((ready >> dep) & 1)) {
              uint32_t n = 0;
              do { __nanosleep(100); ready = poll_flags(fp, target); if (++n > (1u << 23)) {
                asm volatile("trap;"); } } while (!((ready >> dep) & 1));
            }
            if (!smem_free) {
              if (ring_hi_busy) {
                if (cnt == 0) mbar_wait(bars + 8 * B_SFREE, adone_ph);
                if (cnt == 2) { mbar_wait(bars + 8 * B_ADONE, adone_ph); smem_free = true;  }
              } else {
                if (xn_busy) mbar_wait(bars + 8 * B_XDEAD, xdead_ph);
                smem_free = true;
              }
            }
            const int kb = tk.type ? prm.head_order[k >> 1] * 2 + (k & 1) : k;
            mbar_wait(bars + 8 * (B_EMPTY4 + s4), (e4ph >> s4) & 1);
            e4ph ^= (1u << s4);
            if (leader) {
              const uint32_t fb = bars + 8 * (B_FULL4 + s4), dst = sb + t4_off(s4);
              mbar_expect_tx(fb, T4_STAGE);
              bulk_load(dst, abase + (size_t)kb * 16384, 16384, fb);
              const int big = ((cnt & 1) == rank);
              const int b0 = rank == 0 ? 0 : (big ? 2 : 3);
              tma_2d_mc(dst + 16384 + b0 * 4096, mp, fb, tk.j * 160 + b0 * 32, kb * 64);
              tma_2d_mc(dst + 16384 + (b0 + 1) * 4096, mp, fb, tk.j * 160 + (b0 + 1) * 32, kb * 64);
              if (big) tma_2d_mc(dst + 16384 + (b0 + 2) * 4096, mp, fb, tk.j * 160 + (b0 + 2) * 32, kb * 64);
            }
            cnt++;
            s4 = (s4 + 1 == T4_STAGES) ? 0 : s4 + 1;
          }
        }
        const bool last_is_s = sch.t4[sch.nt4 - 1].type != 0;
        const uint32_t u1 = s4 == 0 ? T4_STAGES - 1 : s4 - 1, u2 = u1 == 0 ? T4_STAGES - 1 : u1 - 1;
#pragma unroll 1
        for (uint32_t s = 0; s < T4_STAGES; s++)
          if (!(last_is_s && (s == u1 || s == u2))) mbar_wait(bars + 8 * (B_EMPTY4 + s), (e4ph >> s) & 1);
      } else {
#pragma unroll 1
        for (uint32_t s = 0; s < 8; s++) mbar_wait(bars + 8 * (B_EMPTY + s), (eph >> s) & 1);
        if (ring_hi_busy) mbar_wait(bars + 8 * B_ADONE, adone_ph);
        else if (xn_busy) mbar_wait(bars + 8 * B_XDEAD, xdead_ph);
      }
    } else if (warp <= 2) {
      if (lane == 0) {
        const int w = warp - 1;
        const uint32_t sig = bars + 8 * (B_SIG + w);
        uint32_t ph = 0;
        auto ev = [&](unsigned int* f) { mbar_wait(sig, ph); ph ^= 1; flag_signal(f); };
        for (int sg = 0; sg < sch.nseg; sg++) {
          const Seg seg = sch.seg[sg];
          const int m = 2 * seg.p + rank;
          for (int ci = 0; ci < seg.nc; ci++) ev(&prm.cnt_h[m * 32]);
          if (seg.head0 != 0xFF) {
            for (int hi = 0; hi < 3; hi++) {
              mbar_wait(sig, ph); ph ^= 1;
              const uint32_t src = sb + XN_OFF + w * XN_WG + STASH_OFF + hi * 16384;
              uint8_t* dst = prm.o + ((size_t)m * 64 + (seg.head0 + hi) * 2) * 16384 + w * 8192;
              bulk_store(dst, src, 8192);
              bulk_store(dst + 16384, src + 8192, 8192);
              asm volatile("cp.async.bulk.commit_group;\n\tcp.async.bulk.wait_group 0;" ::: "memory");
              flag_signal(&prm.cnt_o[m * NHEAD + seg.head0 + hi]);
            }
            mbar_arrive_both(bars + 8 * B_SFREE);
            mbar_arrive_both(bars + 8 * B_ADONE);
            ev(&prm.cnt_o[m * NHEAD + seg.head0 + 3]);
          }
        }
      }
    } else {
      const unsigned int ep1 = done / gridDim.x + 1;
      uint32_t xdead_ph = 0, adone_ph = 0;
      bool prev_heads = false;
#pragma unroll 1
      for (int sg = 0; sg < sch.nseg; sg++) {
        const Seg seg = sch.seg[sg];
        const int m = 2 * seg.p + rank;
        if (lane == 0) {
          if (sg > 0) {
            if (prev_heads) { mbar_wait(bars + 8 * B_ADONE, adone_ph); }
            else { mbar_wait(bars + 8 * B_XDEAD, xdead_ph); }
          }
          if (sg > 0) flag_wait_spin(&prm.cnt_xn[m * 32], ep1 * 8);
          asm volatile("fence.proxy.async.global;" ::: "memory");
#pragma unroll 1
          for (int kb = 0; kb < KB_D; kb++) {
            mbar_expect_tx(bars + 8 * (B_XFULL + kb), 16384);
            bulk_load(sb + XN_OFF + kb * 8192, prm.xn + ((size_t)(m * 2 + 0) * KB_D + kb) * 8192, 8192, bars + 8 * (B_XFULL + kb));
            bulk_load(sb + XN_OFF + XN_WG + kb * 8192, prm.xn + ((size_t)(m * 2 + 1) * KB_D + kb) * 8192, 8192, bars + 8 * (B_XFULL + kb));
          }
        }
        if (sg > 0) { if (prev_heads) adone_ph ^= 1; xdead_ph ^= 1; }
        prev_heads = seg.head0 != 0xFF;
        __syncwarp();
      }
    }
    teardown(prm.done);
  } else {
    Ctx c;
    c.sb = sb; c.sd = sb & 0x3FFFFu; c.bars = bars; c.fullph = 0; c.slot = 0; c.w = (warp - 4) >> 2; c.tid = threadIdx.x & 127; c.rank = rank;
#pragma unroll 1
    for (int grp = blockIdx.x; grp < 128; grp += gridDim.x) {
      const int row = grp * 16 + (warp - 4) * 2 + (lane >> 4);
      const int l16 = lane & 15;
      const uint4* xr = reinterpret_cast<const uint4*>(prm.x + (size_t)row * D_MODEL);
      uint4 v[5];
#pragma unroll
      for (int t = 0; t < 5; t++) v[t] = __ldg(xr + l16 + 16 * t);
      float sum = 0.f;
#pragma unroll
      for (int t = 0; t < 5; t++) {
        const uint32_t u[4] = {v[t].x, v[t].y, v[t].z, v[t].w};
#pragma unroll
        for (int e = 0; e < 4; e++) sum += bf_lo(u[e]) + bf_hi(u[e]);
      }
#pragma unroll
      for (int o = 8; o >= 1; o >>= 1) sum += __shfl_xor_sync(0xffffffffu, sum, o);
      const float mean = sum * (1.0f / D_MODEL);
      float sq = 0.f;
#pragma unroll
      for (int t = 0; t < 5; t++) {
        const uint32_t u[4] = {v[t].x, v[t].y, v[t].z, v[t].w};
#pragma unroll
        for (int e = 0; e < 4; e++) { float a = bf_lo(u[e]) - mean, b = bf_hi(u[e]) - mean; sq = fmaf(a, a, sq); sq = fmaf(b, b, sq); }
      }
#pragma unroll
      for (int o = 8; o >= 1; o >>= 1) sq += __shfl_xor_sync(0xffffffffu, sq, o);
      const float mb = round_bf16(mean);
      const float vb = round_bf16(sq * (1.0f / D_MODEL));
      float sq_r; asm("sqrt.approx.f32 %0, %1;" : "=f"(sq_r) : "f"(round_bf16(vb + 1e-5f)));
      const float sd = round_bf16(sq_r);
      float rsd; asm("rcp.approx.f32 %0, %1;" : "=f"(rsd) : "f"(sd));
      const uint32_t mb2 = pack_bf16(mb, mb);
      const int mt = row >> 7, wg = (row >> 6) & 1, r = row & 63;
      uint8_t* dst = prm.xn + (size_t)(mt * 2 + wg) * KB_D * 8192 + r * 128;
#pragma unroll
      for (int t = 0; t < 5; t++) {
        const uint32_t u[4] = {v[t].x, v[t].y, v[t].z, v[t].w};
        uint32_t o4[4];
#pragma unroll
        for (int e = 0; e < 4; e++) {
          uint32_t d; asm("sub.rn.bf16x2 %0, %1, %2;" : "=r"(d) : "r"(u[e]), "r"(mb2));
          o4[e] = pack_bf16(bf_lo(d) * rsd, bf_hi(d) * rsd);
        }
        const int ch = l16 + 16 * t;
        *reinterpret_cast<uint4*>(dst + (ch >> 3) * 8192 + (((ch & 7) ^ (r & 7)) << 4)) = make_uint4(o4[0], o4[1], o4[2], o4[3]);
      }
      bar_sync(6, 256);
      if (threadIdx.x == 128) flag_signal(&prm.cnt_xn[mt * 32]);
    }
    asm volatile("barrier.cluster.wait.acquire.aligned;" ::: "memory");
    asm volatile("setmaxnreg.inc.sync.aligned.u32 232;");
    const uint32_t thr_off = c.w * 8192 + (c.tid >> 5) * 2048 + (c.tid & 31) * 4;
    uint32_t xph = 0;
    for (int sg = 0; sg < sch.nseg; sg++) {
      const Seg seg = sch.seg[sg];
      const int m = 2 * seg.p + rank;
      uint8_t* hbase = prm.h + ((size_t)m * NCHUNK + seg.c0) * 16384 + thr_off;
      const bool has_heads = seg.head0 != 0xFF;
      const int npass = seg.nc + (has_heads ? 1 : 0);
      uint32_t q1[8][4];
#pragma unroll
      for (int k = 0; k < 8; k++) { q1[k][0] = 0; q1[k][1] = 0; q1[k][2] = 0; q1[k][3] = 0; }
#pragma unroll 1
      for (int ps = 0; ps < npass; ps++) {
        float acc[64];
        pass_gemm_prev(c, acc, q1, ps > 0, hbase + (size_t)(ps - 1) * 16384, ps == 0, xph);
        if (ps > 0) signal_event(c);
        pack_frags(acc, q1);
      }
      if (!has_heads) {
        if (c.tid == 0) mbar_arrive_both(bars + 8 * B_XDEAD);
#pragma unroll
        for (int j = 0; j < 8; j++) swiglu_slice(q1, j, hbase + (size_t)(seg.nc - 1) * 16384);
        signal_event(c);
      } else {
        uint32_t q0[8][4], q2[8][4], q3[8][4];
        float acc[64];
        pass_gemm_plain(c, acc, false); pack_frags(acc, q2);
        pass_gemm_plain(c, acc, false); pack_frags(acc, q3);
        pass_gemm_plain(c, acc, true);
        const uint32_t stash = sb + XN_OFF + c.w * XN_WG + STASH_OFF + (c.tid >> 5) * 2048 + (c.tid & 31) * 16;
#pragma unroll
        for (int k = 0; k < 8; k++) {
          const uint32_t a = stash + (k >> 2) * 8192 + (k & 3) * 512;
          asm volatile("st.shared.v4.u32 [%0], {%1,%2,%3,%4};" :: "r"(a), "r"(q1[k][0]), "r"(q1[k][1]), "r"(q1[k][2]), "r"(q1[k][3]) : "memory");
          asm volatile("st.shared.v4.u32 [%0], {%1,%2,%3,%4};" :: "r"(a + 16384), "r"(q2[k][0]), "r"(q2[k][1]), "r"(q2[k][2]), "r"(q2[k][3]) : "memory");
          asm volatile("st.shared.v4.u32 [%0], {%1,%2,%3,%4};" :: "r"(a + 32768), "r"(q3[k][0]), "r"(q3[k][1]), "r"(q3[k][2]), "r"(q3[k][3]) : "memory");
        }
        reg_fence(acc);
        pack_frags(acc, q0);
        attention4(c, q0, prm.o, m, seg.head0);
      }
      xph ^= 1;
    }
    uint32_t s4 = 0, f4ph = 0;
    const int nt4 = __shfl_sync(0xffffffffu, (int)sch.nt4, 0);
    for (int t = 0; t < nt4; t++) {
      T4Task tk;
      tk.type = (uint8_t)__shfl_sync(0xffffffffu, (int)sch.t4[t].type, 0);
      tk.p = (uint8_t)__shfl_sync(0xffffffffu, (int)sch.t4[t].p, 0);
      tk.j = (uint8_t)__shfl_sync(0xffffffffu, (int)sch.t4[t].j, 0);
      const int m = 2 * tk.p + rank;
      const int nkb = tk.type ? 64 : NCHUNK;
      float acc[80];
      uint32_t xr[40];
      const uint32_t q_row0 = (uint32_t)lane / 20u, q_c0 = (uint32_t)lane % 20u;
      const size_t tile_off = ((size_t)(m * 128 + c.w * 64 + (c.tid >> 5) * 16) * D_MODEL + tk.j * 160) * 2;
      {
        const uint8_t* xg = reinterpret_cast<const uint8_t*>(prm.x) + tile_off;
        uint32_t c16 = q_c0, off = q_row0 * (D_MODEL * 2) + q_c0 * 16;
#pragma unroll
        for (int i = 0; i < 10; i++) {
          asm volatile("ld.global.nc.v4.u32 {%0,%1,%2,%3}, [%4];" : "=r"(xr[4 * i]), "=r"(xr[4 * i + 1]), "=r"(xr[4 * i + 2]), "=r"(xr[4 * i + 3])
                       : "l"(xg + off));
          c16 += 12; off += D_MODEL * 2 + 192;
          if (c16 >= 20) { c16 -= 20; off += D_MODEL * 2 - 320; }
        }
      }
      uint32_t prev = 0, prev2 = 0;
      unsigned int done_c;
      asm volatile("ld.relaxed.gpu.global.u32 %0, [%1];" : "=r"(done_c) : "l"(prm.done) : "memory");
#pragma unroll
      for (int i = 0; i < 80; i++) acc[i] = 0.f;
#pragma unroll 1
      for (int k = 0; k < nkb; k++) {
        mbar_wait(bars + 8 * (B_FULL4 + s4), (f4ph >> s4) & 1);
        f4ph ^= (1u << s4);
        const uint32_t st = c.sd + t4_off(s4);
        const uint32_t a_lo = ((st + c.w * 8192) >> 4) | desc_lo_lbo(128);
        const uint32_t b_lo = ((st + 16384) >> 4) | desc_lo_lbo(4096);
        reg_fence(acc);
        wg_fence();
        wgmma_ss_n160_bt(acc, a_lo, HI_NOSWZ, b_lo, HI_SW64, 1);
#pragma unroll
        for (int kk = 1; kk < 4; kk++) wgmma_ss_n160_bt(acc, a_lo + kk * 16, HI_NOSWZ, b_lo + kk * 64, HI_SW64, 1);
        wg_commit();
        if (k > 0) { wg_wait<1>(); if (c.tid == ((k & 3) << 5) && !(tk.type && k == nkb - 1)) mbar_arrive_both(bars + 8 * (B_EMPTY4 + prev)); }
        prev2 = prev;
        prev = s4;
        s4 = (s4 + 1 == T4_STAGES) ? 0 : s4 + 1;
      }
      wg_wait<0>();
      reg_fence(acc);
      if (c.tid == 0 && !tk.type) mbar_arrive_both(bars + 8 * (B_EMPTY4 + prev));
      uint4* gp = reinterpret_cast<uint4*>(prm.g + (size_t)(m * 4 + tk.j) * 40960 + c.w * 20480) + c.tid;
      if (tk.type == 0) {
#pragma unroll
        for (int qd = 0; qd < 10; qd++) {
          uint32_t r[4];
#pragma unroll
          for (int e = 0; e < 4; e++) {
            uint32_t ob = pack_bf16(acc[8 * qd + 2 * e], acc[8 * qd + 2 * e + 1]);
            r[e] = silu_pair(ob);
          }
          gp[qd * 128] = make_uint4(r[0], r[1], r[2], r[3]);
        }
        bar_sync(3 + c.w, 128);
        if (c.tid == 0) flag_signal(&prm.cnt_g[m * 4 + tk.j]);
      } else {
        if (c.tid == 0 && c.w == 0) flag_wait(&prm.cnt_g[m * 4 + tk.j], (done_c / gridDim.x + 1) * 2);
        bar_sync(5, 256);
        uint32_t gr[40];
#pragma unroll
        for (int qd = 0; qd < 10; qd++)
          asm volatile("ld.global.cg.v4.u32 {%0,%1,%2,%3}, [%4];" : "=r"(gr[4 * qd]), "=r"(gr[4 * qd + 1]), "=r"(gr[4 * qd + 2]), "=r"(gr[4 * qd + 3]) : "l"(gp + qd * 128) : "memory");
        const uint32_t ln = c.tid & 31, rr = (c.tid >> 5) * 16 + (ln & 7) + ((ln >> 3) & 1) * 8;
        const uint32_t stg0 = sb + t4_off(c.w ? prev : prev2);
        const uint32_t stg = stg0 + rr * 64;
#pragma unroll
        for (int qd = 0; qd < 10; qd++) {
          uint32_t y[4];
#pragma unroll
          for (int e = 0; e < 4; e++) {
            const int idx = 4 * qd + e;
            y[e] = mul_bf16x2(pack_bf16(acc[2 * idx], acc[2 * idx + 1]), gr[idx]);
          }
          const uint32_t jj = 2 * qd + (ln >> 4);
          const uint32_t a = stg + (jj >> 2) * 4096 + (((jj & 3) ^ ((rr >> 1) & 3)) << 4);
          asm volatile("stmatrix.sync.aligned.m8n8.x4.shared.b16 [%0], {%1,%2,%3,%4};" :: "r"(a), "r"(y[0]), "r"(y[1]), "r"(y[2]), "r"(y[3]) : "memory");
        }
        __syncwarp();
        {
          uint8_t* yg = reinterpret_cast<uint8_t*>(prm.out) + tile_off;
          uint32_t row = q_row0 + (c.tid >> 5) * 16, c16 = q_c0, off = q_row0 * (D_MODEL * 2) + q_c0 * 16;
#pragma unroll
          for (int i = 0; i < 10; i++) {
            uint32_t t0, t1, t2, t3;
            asm volatile("ld.shared.v4.u32 {%0,%1,%2,%3}, [%4];" : "=r"(t0), "=r"(t1), "=r"(t2), "=r"(t3)
                         : "r"(stg0 + (c16 >> 2) * 4096 + row * 64 + (((c16 & 3) ^ ((row >> 1) & 3)) << 4)) : "memory");
            *reinterpret_cast<uint4*>(yg + off) = make_uint4(add_bf16x2(xr[4 * i], t0), add_bf16x2(xr[4 * i + 1], t1), add_bf16x2(xr[4 * i + 2], t2), add_bf16x2(xr[4 * i + 3], t3));
            row += 1; c16 += 12; off += D_MODEL * 2 + 192;
            if (c16 >= 20) { c16 -= 20; row += 1; off += D_MODEL * 2 - 320; }
          }
        }
        if (t + 1 < nt4) {
          bar_sync(5, 256);
          if (c.tid == 0) {
            mbar_arrive_both(bars + 8 * (B_EMPTY4 + prev));
            mbar_arrive_both(bars + 8 * (B_EMPTY4 + prev2));
          }
        }
      }
    }
    teardown(prm.done);
  }
}

typedef CUresult (*EncodeFn)(CUtensorMap*, CUtensorMapDataType, cuuint32_t, void*, const cuuint64_t*, const cuuint64_t*, const cuuint32_t*,
                             const cuuint32_t*, CUtensorMapInterleave, CUtensorMapSwizzle, CUtensorMapL2promotion, CUtensorMapFloatOOBfill);

static bool make_map(EncodeFn fn, CUtensorMap* m, const void* ptr, uint64_t cols, uint64_t rows, uint32_t box_c, uint32_t box_r, CUtensorMapSwizzle sw) {
  cuuint64_t dims[2] = {cols, rows};
  cuuint64_t strides[1] = {cols * 2};
  cuuint32_t box[2] = {box_c, box_r};
  cuuint32_t es[2] = {1, 1};
  return fn(m, CU_TENSOR_MAP_DATA_TYPE_BFLOAT16, 2, const_cast<void*>(ptr), dims, strides, box, es, CU_TENSOR_MAP_INTERLEAVE_NONE, sw,
            CU_TENSOR_MAP_L2_PROMOTION_L2_256B, CU_TENSOR_MAP_FLOAT_OOB_FILL_NONE) == CUDA_SUCCESS;
}

__global__ void probe_kernel() {}
#define SCHED_CODE 11115555
static int sched_nch(int type) { int v = SCHED_CODE; for (int t = 7; t > type; t--) v /= 10; return v % 10; }
static void build_schedule(Params& P, int npairs, int map_k, int map_shift, int map_goff) {
  {
    int k = 0;
    for (int grp = 0; grp < 2; grp++) for (int i = 0; i < 4; i++) for (int f = 0; f < 4; f++) P.head_order[k++] = (uint8_t)(grp * 16 + f * 4 + i);
  }
  for (int i = 0; i < MAX_PAIRS; i++) { P.sched[i].nseg = 0; P.sched[i].nt4 = 0; }
  if (npairs >= 66) {
    for (int cl = 0; cl < 66; cl++) {
      const int t = (cl + map_shift) % 66;
      int type, p;
      if (t < 32) { type = t >> 3; p = t & 7; }
      else if (t < 32 + 4 * map_k) {
        const int u = t - 32;
        type = 4 + u / map_k; p = (u % map_k + map_goff) & 7;
      } else {
        const int u = t - 32 - 4 * map_k;
        const int missing = 32 - 4 * map_k;
        if (u < missing) { type = 4 + (u & 3); p = (map_k + (u >> 2) + map_goff) & 7; } else { type = 8; p = u - missing; }
      }
      const int c = cl;
      if (type == 8) {
        PairSched& s = P.sched[c];
        s.nseg = 4; s.nt4 = 0;
        int used = 0;
        for (int q = 0; q < 8; q++) used += sched_nch(q);
        for (int i = 0; i < 4; i++) s.seg[i] = Seg{(uint8_t)(p * 4 + i), (uint8_t)used, (uint8_t)(NCHUNK - used), 0xFF};
        continue;
      }
      PairSched& s = P.sched[c];
      s.nseg = 1; s.nt4 = 1;
      int c0 = 0;
      for (int t = 0; t < type; t++) c0 += sched_nch(t);
      s.seg[0] = Seg{(uint8_t)p, (uint8_t)c0, (uint8_t)sched_nch(type), (uint8_t)(4 * type)};
      if (type < 4) s.t4[0] = T4Task{1, (uint8_t)p, (uint8_t)type, 0};
      else          s.t4[0] = T4Task{0, (uint8_t)p, (uint8_t)(type - 4), 0};
    }
  } else {
    for (int i = 0; i < 64; i++) {
      const int p = i >> 3, g = i & 7;
      const int nc = g < 3 ? 4 : 3, c0 = g < 3 ? 4 * g : 12 + 3 * (g - 3);
      PairSched& s = P.sched[i % npairs];
      s.seg[s.nseg++] = Seg{(uint8_t)p, (uint8_t)c0, (uint8_t)nc, (uint8_t)(4 * g)};
    }
    for (int i = 0; i < 64; i++) {
      PairSched& s = P.sched[(i + 64) % npairs];
      s.t4[s.nt4++] = T4Task{(uint8_t)(i >> 5), (uint8_t)((i & 31) >> 2), (uint8_t)(i & 3), 0};
    }
  }
}

}

extern "C" void kernel_launch(void* const* d_in, const int* in_sizes, int n_in, void* d_out, int out_size) {
  using namespace fk;
  (void)in_sizes; (void)n_in; (void)out_size;
  static bool inited = false;
  static CUtensorMap m_wq, m_w1, m_w3, m_k, m_v, m_wo, m_w2;
  static Params prm;
  static void* cached[10];
  static int npairs = 66;
  bool same = inited;
  for (int i = 0; i < 9 && same; i++) same = cached[i] == d_in[i];
  same = same && cached[9] == d_out;
  if (!same) {
    void* fnp = nullptr;
    cudaDriverEntryPointQueryResult qr;
    cudaGetDriverEntryPoint("cuTensorMapEncodeTiled", &fnp, cudaEnableDefault, &qr);
    EncodeFn fn = (EncodeFn)fnp;
    make_map(fn, &m_k, d_in[1], DH, (uint64_t)NHEAD * SK, 64, 64, CU_TENSOR_MAP_SWIZZLE_128B);
    make_map(fn, &m_v, d_in[2], DH, (uint64_t)NHEAD * SK, 64, 64, CU_TENSOR_MAP_SWIZZLE_128B);
    make_map(fn, &m_wq, d_in[3], NHEAD * DH, D_MODEL, 64, 64, CU_TENSOR_MAP_SWIZZLE_128B);
    make_map(fn, &m_wo, d_in[4], D_MODEL, NHEAD * DH, 32, 64, CU_TENSOR_MAP_SWIZZLE_64B);
    make_map(fn, &m_w1, d_in[6], F_FF, D_MODEL, 64, 64, CU_TENSOR_MAP_SWIZZLE_128B);
    make_map(fn, &m_w3, d_in[7], F_FF, D_MODEL, 64, 64, CU_TENSOR_MAP_SWIZZLE_128B);
    make_map(fn, &m_w2, d_in[8], D_MODEL, F_FF, 32, 64, CU_TENSOR_MAP_SWIZZLE_64B);
    prm.x = (const __nv_bfloat16*)d_in[0];
    prm.out = (__nv_bfloat16*)d_out;
    void* sp;
    cudaGetSymbolAddress(&sp, g_xn); prm.xn = (uint8_t*)sp;
    cudaGetSymbolAddress(&sp, g_h); prm.h = (uint8_t*)sp;
    cudaGetSymbolAddress(&sp, g_o); prm.o = (uint8_t*)sp;
    cudaGetSymbolAddress(&sp, g_g); prm.g = (uint8_t*)sp;
    cudaGetSymbolAddress(&sp, g_cnt_xn); prm.cnt_xn = (unsigned int*)sp;
    cudaGetSymbolAddress(&sp, g_cnt_h); prm.cnt_h = (unsigned int*)sp;
    cudaGetSymbolAddress(&sp, g_cnt_o); prm.cnt_o = (unsigned int*)sp;
    cudaGetSymbolAddress(&sp, g_cnt_g); prm.cnt_g = (unsigned int*)sp;
    cudaGetSymbolAddress(&sp, g_done); prm.done = (unsigned int*)sp;
    cudaFuncSetAttribute(fused_kernel, cudaFuncAttributeMaxDynamicSharedMemorySize, SMEM_BYTES);
    npairs = 66;
    {
      cudaLaunchConfig_t cfg = {};
      cfg.gridDim = dim3(132); cfg.blockDim = dim3(384); cfg.dynamicSmemBytes = SMEM_BYTES;
      cudaLaunchAttribute at[1];
      at[0].id = cudaLaunchAttributeClusterDimension; at[0].val.clusterDim.x = 2; at[0].val.clusterDim.y = 1; at[0].val.clusterDim.z = 1;
      cfg.attrs = at; cfg.numAttrs = 1;
      int nc = 0;
      if (cudaOccupancyMaxActiveClusters(&nc, fused_kernel, &cfg) == cudaSuccess && nc > 0 && nc < npairs) npairs = nc;
      (void)cudaGetLastError();
    }
    if (npairs < 16) npairs = 16;
    int k5 = 0;
    {
      cudaFuncSetAttribute(probe_kernel, cudaFuncAttributeNonPortableClusterSizeAllowed, 1);
      cudaFuncSetAttribute(probe_kernel, cudaFuncAttributeMaxDynamicSharedMemorySize, 200 * 1024);
      cudaLaunchConfig_t cfg = {};
      cfg.gridDim = dim3(80); cfg.blockDim = dim3(128); cfg.dynamicSmemBytes = 200 * 1024;
      cudaLaunchAttribute at[1];
      at[0].id = cudaLaunchAttributeClusterDimension; at[0].val.clusterDim.x = 10; at[0].val.clusterDim.y = 1; at[0].val.clusterDim.z = 1;
      cfg.attrs = at; cfg.numAttrs = 1;
      if (cudaOccupancyMaxActiveClusters(&k5, probe_kernel, &cfg) != cudaSuccess) k5 = 0;
      (void)cudaGetLastError();
    }
    if (k5 == 7) build_schedule(prm, npairs, 7, 62, 1);
    else         build_schedule(prm, npairs, 8, 0, 0);
    for (int i = 0; i < 9; i++) cached[i] = d_in[i];
    cached[9] = d_out;
    inited = true;
  }
  fused_kernel<<<2 * npairs, 384, SMEM_BYTES, cudaStreamPerThread>>>(m_wq, m_w1, m_w3, m_k, m_v, m_wo, m_w2, prm);
}
```
